```python
import torch

def _softmax(x, axis=-1):
    return torch.softmax(x, dim=axis)
def _gelu(x):
    return torch.nn.functional.gelu(x, approximate="tanh")
def _silu(x):
    return torch.nn.functional.silu(x)
def _sigmoid(x):
    return torch.sigmoid(x)
def _layernorm(x, axis=-1, eps=1e-5):
    m = x.mean(dim=axis, keepdim=True)
    v = x.var(dim=axis, keepdim=True, unbiased=False)
    return (x - m) / torch.sqrt(v + eps)
def _scatter_add(tgt, idx, src, axis=0):
    return tgt.clone().index_add_(axis, idx, src)
def _segment_sum(src, seg, n):
    out = torch.zeros((n,) + src.shape[1:], dtype=src.dtype)
    return out.index_add_(0, seg, src)
def _pad(x, pw):
    flat = tuple(v for pair in reversed(pw) for v in pair)
    return torch.nn.functional.pad(x, flat)

kernel_name = 'standalone__seq2seq_rnn_t_joint__speech'

def setup_inputs():

    _w = (lambda a: (lambda t: t.to(torch.bfloat16) if t.is_floating_point() else t)(torch.as_tensor(a)))
    B, T, D, K = 2, 4000, 256, 3
    U = 8
    sc = (1.0 / (K * D)) ** 0.5
    sd = (1.0 / D) ** 0.5
    return {
        "x": _w((lambda *s: torch.randn(*s, dtype=torch.bfloat16) * 0.2)(B, T, D) * 0.5),
        "w1": _w((lambda *s: torch.randn(*s, dtype=torch.bfloat16) * 3.2)(K, D, D) * sc),
        "w2": _w((lambda *s: torch.randn(*s, dtype=torch.bfloat16) * 3.2)(K, D, D) * sc),
        "g": _w((lambda *s: torch.randn(*s, dtype=torch.bfloat16) * 3.2)(B, U, D) * 0.5),
        "w_f": _w((lambda *s: torch.randn(*s, dtype=torch.bfloat16) * 3.2)(D, D) * sd),
        "w_g": _w((lambda *s: torch.randn(*s, dtype=torch.bfloat16) * 3.2)(D, D) * sd),
        "w_o": _w((lambda *s: torch.randn(*s, dtype=torch.bfloat16) * 3.2)(D, D) * sd),
    }

def reference(x, w1, w2, g, w_f, w_g, w_o):
    B, T, D = x.shape
    K = w1.shape[0]
    pad = K // 2
    xp = _pad(x, ((0,0),(pad,pad),(0,0)))
    h = torch.zeros_like(x)
    for i in range(K):
        h = h + torch.einsum("btc,cd->btd", xp[:, i:i+T, :], w1[i])
    h = _gelu(h)[:, ::2, :]
    T1 = h.shape[1]
    hp = _pad(h, ((0,0),(pad,pad),(0,0)))
    f = torch.zeros_like(h)
    for i in range(K):
        f = f + torch.einsum("btc,cd->btd", hp[:, i:i+T1, :], w2[i])
    f = _gelu(f)[:, ::2, :]
    fe = torch.einsum("btd,de->bte", f, w_f)
    ge = torch.einsum("bud,de->bue", g, w_g)
    j = torch.tanh(fe[:, :, None, :] + ge[:, None, :, :])
    return torch.einsum("btud,dv->btuv", j, w_o)
```

```cpp
#include <cuda_runtime.h>
#include <cuda.h>
#include <cuda_bf16.h>
#include <stdint.h>

namespace {

constexpr int kR = 31;
constexpr int kTilesPerB = 33;
constexpr int kT2 = 1000;
constexpr int kSlots = 8;
constexpr int XDELAY = 2000;
constexpr int XSTEP = 800;

constexpr uint32_t OFF_X    = 0;
constexpr uint32_t OFF_F    = 0;
constexpr uint32_t OFF_FR   = 57344;
constexpr uint32_t FE_PITCH = 528;
constexpr uint32_t OFF_FE   = 8192;
constexpr uint32_t OFF_GE   = OFF_FE + 16 * FE_PITCH;
constexpr uint32_t OFF_E    = 8192;
constexpr uint32_t OFF_H    = 65536;
constexpr uint32_t OFF_RING = 98304;
constexpr uint32_t OFF_STG2 = OFF_RING + 6 * 16384;
constexpr uint32_t OFF_BAR  = OFF_RING + kSlots * 16384;
constexpr uint32_t BAR_FULL  = OFF_BAR;
constexpr uint32_t BAR_EMPTY = BAR_FULL + 8 * kSlots;
constexpr uint32_t BAR_X     = BAR_EMPTY + 8 * kSlots;
constexpr uint32_t BAR_H     = BAR_X + 32;
constexpr uint32_t BAR_P     = BAR_H + 32;
constexpr uint32_t BAR_WO    = BAR_P + 8;
constexpr uint32_t BAR_G     = BAR_WO + 8;
constexpr uint32_t BAR_XF    = BAR_G + 8;
constexpr uint32_t BAR_E     = BAR_XF + 8;
constexpr uint32_t BAR_WA    = BAR_E + 24;
constexpr uint32_t SMEM_USED = OFF_BAR + 256;
constexpr uint32_t SMEM_BYTES = SMEM_USED + 1024;

__device__ __forceinline__ uint32_t smem_u32(const void* p) { return (uint32_t)__cvta_generic_to_shared(p); }
__device__ __forceinline__ void mbar_init(uint32_t bar, uint32_t cnt) {
  asm volatile("mbarrier.init.shared::cta.b64 [%0], %1;" ::"r"(bar), "r"(cnt) : "memory");
}
__device__ __forceinline__ void mbar_expect_tx(uint32_t bar, uint32_t bytes) {
  asm volatile("mbarrier.arrive.expect_tx.shared::cta.b64 _, [%0], %1;" ::"r"(bar), "r"(bytes) : "memory");
}
__device__ __forceinline__ void mbar_arrive(uint32_t bar) {
  asm volatile("mbarrier.arrive.shared::cta.b64 _, [%0];" ::"r"(bar) : "memory");
}
__device__ __forceinline__ void mbar_wait(uint32_t bar, uint32_t parity) {
  uint32_t done;
  uint32_t it = 0;
  do {
    asm volatile(
        "{\n.reg .pred p;\nmbarrier.try_wait.parity.shared::cta.b64 p, [%1], %2;\nselp.u32 %0, 1, 0, p;\n}\n"
        : "=r"(done)
        : "r"(bar), "r"(parity)
        : "memory");
  } while (!done && ++it < (1u << 18));
}
__device__ __forceinline__ void mbar_wait_cluster(uint32_t bar, uint32_t parity) {
  uint32_t done;
  uint32_t it = 0;
  do {
    asm volatile(
        "{\n.reg .pred p;\nmbarrier.try_wait.parity.acquire.cluster.shared::cta.b64 p, [%1], %2;\nselp.u32 %0, 1, 0, p;\n}\n"
        : "=r"(done)
        : "r"(bar), "r"(parity)
        : "memory");
  } while (!done && ++it < (1u << 18));
}
__device__ __forceinline__ uint32_t mapa(uint32_t addr, uint32_t rank) {
  uint32_t r;
  asm volatile("mapa.shared::cluster.u32 %0, %1, %2;" : "=r"(r) : "r"(addr), "r"(rank));
  return r;
}
__device__ __forceinline__ void tma3d(uint32_t dst, const CUtensorMap* m, int c0, int c1, int c2, uint32_t bar) {
  asm volatile(
      "cp.async.bulk.tensor.3d.shared::cluster.global.mbarrier::complete_tx::bytes [%0], [%1, {%3, %4, %5}], [%2];" ::"r"(dst),
      "l"(m), "r"(bar), "r"(c0), "r"(c1), "r"(c2)
      : "memory");
}
__device__ __forceinline__ void tma4d(uint32_t dst, const CUtensorMap* m, int c0, int c1, int c2, int c3, uint32_t bar) {
  asm volatile(
      "cp.async.bulk.tensor.4d.shared::cluster.global.mbarrier::complete_tx::bytes [%0], [%1, {%3, %4, %5, %6}], [%2];" ::"r"(dst),
      "l"(m), "r"(bar), "r"(c0), "r"(c1), "r"(c2), "r"(c3)
      : "memory");
}
__device__ __forceinline__ void tma_store3d(const CUtensorMap* m, uint32_t src, int c0, int c1, int c2) {
  asm volatile("cp.async.bulk.tensor.3d.global.shared::cta.bulk_group [%0, {%2, %3, %4}], [%1];" ::"l"(m), "r"(src), "r"(c0),
               "r"(c1), "r"(c2)
               : "memory");
}
__device__ __forceinline__ void bulk_s2s(uint32_t dst_cluster, uint32_t src, uint32_t bytes, uint32_t bar_cluster) {
  asm volatile("cp.async.bulk.shared::cluster.shared::cta.mbarrier::complete_tx::bytes [%0], [%1], %2, [%3];" ::"r"(dst_cluster),
               "r"(src), "r"(bytes), "r"(bar_cluster)
               : "memory");
}
__device__ __forceinline__ void st_async_v4(uint32_t dst_cluster, float a, float b, float c, float d, uint32_t bar_cluster) {
  asm volatile("st.async.weak.shared::cluster.mbarrier::complete_tx::bytes.v4.f32 [%0], {%1, %2, %3, %4}, [%5];" ::"r"(dst_cluster),
               "f"(a), "f"(b), "f"(c), "f"(d), "r"(bar_cluster)
               : "memory");
}
__device__ __forceinline__ void prefetch_map(const CUtensorMap* m) {
  asm volatile("prefetch.tensormap [%0];" ::"l"(m) : "memory");
}
__device__ __forceinline__ void prefetch_l2(const void* p, uint32_t bytes) {
  asm volatile("cp.async.bulk.prefetch.L2.global [%0], %1;" ::"l"(p), "r"(bytes) : "memory");
}
__device__ __forceinline__ void fence_async() { asm volatile("fence.proxy.async.shared::cta;" ::: "memory"); }
template <int ID, int N> __device__ __forceinline__ void bar_sync() { asm volatile("bar.sync %0, %1;" ::"n"(ID), "n"(N) : "memory"); }
template <int ID, int N> __device__ __forceinline__ void bar_arrive() { asm volatile("bar.arrive %0, %1;" ::"n"(ID), "n"(N) : "memory"); }
__device__ __forceinline__ void wg_fence() { asm volatile("wgmma.fence.sync.aligned;" ::: "memory"); }
__device__ __forceinline__ void wg_commit() { asm volatile("wgmma.commit_group.sync.aligned;" ::: "memory"); }
template <int N>
__device__ __forceinline__ void wg_wait() { asm volatile("wgmma.wait_group.sync.aligned %0;" ::"n"(N) : "memory"); }

__device__ __forceinline__ uint32_t desc_mn(uint32_t addr) { return ((addr & 0x3FFFFu) >> 4) | (512u << 16); }
__device__ __forceinline__ uint32_t desc_k(uint32_t addr) { return ((addr & 0x3FFFFu) >> 4) | (1u << 16); }
__device__ __forceinline__ float tanh_fast(float x) {
  float y;
  asm("tanh.approx.f32 %0, %1;" : "=f"(y) : "f"(x));
  return y;
}
__device__ __forceinline__ float gelu_tanh(float x) {
  const float k0 = 0.7978845608028654f, k1 = 0.7978845608028654f * 0.044715f;
  float u = x * __fmaf_rn(k1, x * x, k0);
  float hx = 0.5f * x;
  return __fmaf_rn(hx, tanh_fast(u), hx);
}
__device__ __forceinline__ uint32_t pack_bf16(float lo, float hi) {
  uint32_t r;
  asm("cvt.rn.bf16x2.f32 %0, %1, %2;" : "=r"(r) : "f"(hi), "f"(lo));
  return r;
}
__device__ __forceinline__ uint32_t joint2(uint32_t a, uint32_t b) {
  uint32_t s;
  asm("add.rn.bf16x2 %0, %1, %2;" : "=r"(s) : "r"(a), "r"(b));
  float lo = __uint_as_float(s << 16), hi = __uint_as_float(s & 0xffff0000u);
  return pack_bf16(tanh_fast(lo), tanh_fast(hi));
}
__device__ __forceinline__ void stsm_x4(uint32_t addr, uint32_t r0, uint32_t r1, uint32_t r2, uint32_t r3) {
  asm volatile("stmatrix.sync.aligned.m8n8.x4.shared.b16 [%0], {%1, %2, %3, %4};" ::"r"(addr), "r"(r0), "r"(r1), "r"(r2), "r"(r3) : "memory");
}
__device__ __forceinline__ void stsm_x4_t(uint32_t addr, uint32_t r0, uint32_t r1, uint32_t r2, uint32_t r3) {
  asm volatile("stmatrix.sync.aligned.m8n8.x4.trans.shared.b16 [%0], {%1, %2, %3, %4};" ::"r"(addr), "r"(r0), "r"(r1), "r"(r2), "r"(r3) : "memory");
}
__device__ __forceinline__ void ldsm_x4(uint32_t addr, uint32_t& r0, uint32_t& r1, uint32_t& r2, uint32_t& r3) {
  asm volatile("ldmatrix.sync.aligned.m8n8.x4.shared.b16 {%0, %1, %2, %3}, [%4];" : "=r"(r0), "=r"(r1), "=r"(r2), "=r"(r3) : "r"(addr) : "memory");
}
__device__ __forceinline__ uint32_t lds32(uint32_t addr) {
  uint32_t v;
  asm volatile("ld.shared.u32 %0, [%1];" : "=r"(v) : "r"(addr) : "memory");
  return v;
}
__device__ __forceinline__ float4 lds128(uint32_t addr) {
  float4 v;
  asm volatile("ld.shared.v4.f32 {%0, %1, %2, %3}, [%4];" : "=f"(v.x), "=f"(v.y), "=f"(v.z), "=f"(v.w) : "r"(addr) : "memory");
  return v;
}

template<int TA, int TB>
__device__ __forceinline__ void wgmma_ss_n64(float (&d)[32], uint32_t da, uint32_t db, int scale_d) {
  asm volatile("{\n.reg .pred p;\n.reg .b64 da, db;\nsetp.ne.b32 p, %34, 0;\nmov.b64 da, {%32, 0x40000040};\nmov.b64 db, {%33, 0x40000040};\n"
    "wgmma.mma_async.sync.aligned.m64n64k16.f32.bf16.bf16 {%0, %1, %2, %3, %4, %5, %6, %7, %8, %9, %10, %11, %12, %13, %14, %15, %16, %17, %18, %19, %20, %21, %22, %23, %24, %25, %26, %27, %28, %29, %30, %31}, da, db, p, 1, 1, %35, %36;\n}\n"
    : "+f"(d[0]), "+f"(d[1]), "+f"(d[2]), "+f"(d[3]), "+f"(d[4]), "+f"(d[5]), "+f"(d[6]), "+f"(d[7]), "+f"(d[8]), "+f"(d[9]), "+f"(d[10]), "+f"(d[11]), "+f"(d[12]), "+f"(d[13]), "+f"(d[14]), "+f"(d[15]), "+f"(d[16]), "+f"(d[17]), "+f"(d[18]), "+f"(d[19]), "+f"(d[20]), "+f"(d[21]), "+f"(d[22]), "+f"(d[23]), "+f"(d[24]), "+f"(d[25]), "+f"(d[26]), "+f"(d[27]), "+f"(d[28]), "+f"(d[29]), "+f"(d[30]), "+f"(d[31])
    : "r"(da), "r"(db), "r"(scale_d), "n"(TA), "n"(TB));
}
template<int TA, int TB>
__device__ __forceinline__ void wgmma_ss_n32(float (&d)[16], uint32_t da, uint32_t db, int scale_d) {
  asm volatile("{\n.reg .pred p;\n.reg .b64 da, db;\nsetp.ne.b32 p, %18, 0;\nmov.b64 da, {%16, 0x40000040};\nmov.b64 db, {%17, 0x40000040};\n"
    "wgmma.mma_async.sync.aligned.m64n32k16.f32.bf16.bf16 {%0, %1, %2, %3, %4, %5, %6, %7, %8, %9, %10, %11, %12, %13, %14, %15}, da, db, p, 1, 1, %19, %20;\n}\n"
    : "+f"(d[0]), "+f"(d[1]), "+f"(d[2]), "+f"(d[3]), "+f"(d[4]), "+f"(d[5]), "+f"(d[6]), "+f"(d[7]), "+f"(d[8]), "+f"(d[9]), "+f"(d[10]), "+f"(d[11]), "+f"(d[12]), "+f"(d[13]), "+f"(d[14]), "+f"(d[15])
    : "r"(da), "r"(db), "r"(scale_d), "n"(TA), "n"(TB));
}
template<int TA, int TB>
__device__ __forceinline__ void wgmma_ss_n16(float (&d)[8], uint32_t da, uint32_t db, int scale_d) {
  asm volatile("{\n.reg .pred p;\n.reg .b64 da, db;\nsetp.ne.b32 p, %10, 0;\nmov.b64 da, {%8, 0x40000040};\nmov.b64 db, {%9, 0x40000040};\n"
    "wgmma.mma_async.sync.aligned.m64n16k16.f32.bf16.bf16 {%0, %1, %2, %3, %4, %5, %6, %7}, da, db, p, 1, 1, %11, %12;\n}\n"
    : "+f"(d[0]), "+f"(d[1]), "+f"(d[2]), "+f"(d[3]), "+f"(d[4]), "+f"(d[5]), "+f"(d[6]), "+f"(d[7])
    : "r"(da), "r"(db), "r"(scale_d), "n"(TA), "n"(TB));
}
template<int TA, int TB>
__device__ __forceinline__ void wgmma_ss_n8(float (&d)[4], uint32_t da, uint32_t db, int scale_d) {
  asm volatile("{\n.reg .pred p;\n.reg .b64 da, db;\nsetp.ne.b32 p, %6, 0;\nmov.b64 da, {%4, 0x40000040};\nmov.b64 db, {%5, 0x40000040};\n"
    "wgmma.mma_async.sync.aligned.m64n8k16.f32.bf16.bf16 {%0, %1, %2, %3}, da, db, p, 1, 1, %7, %8;\n}\n"
    : "+f"(d[0]), "+f"(d[1]), "+f"(d[2]), "+f"(d[3])
    : "r"(da), "r"(db), "r"(scale_d), "n"(TA), "n"(TB));
}
template<int TB>
__device__ __forceinline__ void wgmma_rs_n64(float (&d)[32], uint32_t a0, uint32_t a1, uint32_t a2, uint32_t a3, uint32_t db, int scale_d) {
  asm volatile("{\n.reg .pred p;\n.reg .b64 db;\nsetp.ne.b32 p, %37, 0;\nmov.b64 db, {%36, 0x40000040};\n"
    "wgmma.mma_async.sync.aligned.m64n64k16.f32.bf16.bf16 {%0, %1, %2, %3, %4, %5, %6, %7, %8, %9, %10, %11, %12, %13, %14, %15, %16, %17, %18, %19, %20, %21, %22, %23, %24, %25, %26, %27, %28, %29, %30, %31}, {%32, %33, %34, %35}, db, p, 1, 1, %38;\n}\n"
    : "+f"(d[0]), "+f"(d[1]), "+f"(d[2]), "+f"(d[3]), "+f"(d[4]), "+f"(d[5]), "+f"(d[6]), "+f"(d[7]), "+f"(d[8]), "+f"(d[9]), "+f"(d[10]), "+f"(d[11]), "+f"(d[12]), "+f"(d[13]), "+f"(d[14]), "+f"(d[15]), "+f"(d[16]), "+f"(d[17]), "+f"(d[18]), "+f"(d[19]), "+f"(d[20]), "+f"(d[21]), "+f"(d[22]), "+f"(d[23]), "+f"(d[24]), "+f"(d[25]), "+f"(d[26]), "+f"(d[27]), "+f"(d[28]), "+f"(d[29]), "+f"(d[30]), "+f"(d[31])
    : "r"(a0), "r"(a1), "r"(a2), "r"(a3), "r"(db), "r"(scale_d), "n"(TB));
}

__global__ void __cluster_dims__(2, 1, 1) __launch_bounds__(384, 1)
joint_kernel(const __grid_constant__ CUtensorMap mx, const __grid_constant__ CUtensorMap mw1,
             const __grid_constant__ CUtensorMap mw2, const __grid_constant__ CUtensorMap mwf,
             const __grid_constant__ CUtensorMap mwg, const __grid_constant__ CUtensorMap mwo,
             const __grid_constant__ CUtensorMap mg, const __grid_constant__ CUtensorMap mout,
             const __grid_constant__ CUtensorMap mout8,
             const uint8_t* __restrict__ pw2, const uint8_t* __restrict__ pwf, const uint8_t* __restrict__ pwo) {
  extern __shared__ uint8_t smem_raw[];
  const long long t_start = clock64();
  const uint32_t sb = (smem_u32(smem_raw) + 1023u) & ~1023u;
  const int tid = threadIdx.x;
  const int lane = tid & 31;
  const int warp = __shfl_sync(0xffffffffu, tid >> 5, 0);
  uint32_t r;
  asm volatile("mov.u32 %0, %%cluster_ctarank;" : "=r"(r));
  const int cl = blockIdx.x >> 1;
  const int b = cl / kTilesPerB;
  const int a = (cl - b * kTilesPerB) * kR;
  const int r2 = 2 * r;
  const uint32_t off_g = OFF_H + r2 * 8192;

  if (warp < 8) {
  if (lane == 0) {
    mbar_init(sb + BAR_EMPTY + 8 * warp, 8);
    const uint32_t mybar = sb + BAR_H + 8 * warp;
    mbar_init(mybar, warp == 5 ? 4 : warp == 7 ? 8 : 1);
    if ((warp >> 1) == (int)(r ^ 1) || warp == 6) mbar_expect_tx(mybar, 8192);
    if (warp == 4) mbar_expect_tx(mybar, 4096);
    asm volatile("fence.mbarrier_init.release.cluster;" ::: "memory");
    if (warp == 0) prefetch_map(&mx);
    else if (warp == 1) prefetch_map(&mw1);
    else if (warp == 2) prefetch_map(&mg);
  }
  bar_sync<4, 384>();
  asm volatile("barrier.cluster.arrive.relaxed.aligned;" ::: "memory");
  const int w = warp >> 2;
  const int wq = warp & 3;
  const int l8 = lane & 7, mi = lane >> 3;
  const uint32_t ring = sb + OFF_RING;
  const uint32_t adesc = desc_mn(ring + w * 8192);

#define WAIT_FULL(slot, use, tr) mbar_wait(sb + BAR_FULL + 8 * (slot), (use) & 1)
#define RELEASE(slot) do { if (lane == 0) mbar_arrive(sb + BAR_EMPTY + 8 * (slot)); } while (0)
#define ADESC(slot, ks) (adesc + (slot) * 1024 + (ks) * 128)
#define W1_SLOT(j) ((4 + (j)) & 7)
#define W1_USE(j) ((4 + (j)) >> 3)
#define W2_SLOT(j) ((16 + (j)) & 7)
#define W2_USE(j) ((16 + (j)) >> 3)

  float ag[2][4];
  {
    const uint32_t gdesc = desc_k(sb + off_g);
    WAIT_FULL(2, 0, 2);
#pragma unroll
    for (int j = 0; j < 4; j++) {
      if (j != 2) WAIT_FULL(j, 0, j);
      wg_fence();
#pragma unroll
      for (int ks = 0; ks < 4; ks++) wgmma_ss_n8<1, 0>(ag[j & 1], ADESC(j, ks), gdesc + (j >> 1) * 64 + ks * 2, ((j >> 1) | ks) != 0);
      wg_commit();
      if (j > 0) { wg_wait<1>(); RELEASE(j - 1); }
    }
    wg_wait<0>();
    RELEASE(3);
    asm volatile("barrier.cluster.wait.acquire.aligned;" ::: "memory");
    const uint32_t gdst = mapa(sb + OFF_H + (r2 ^ 2) * 8192 + 4096 + tid * 16, r ^ 1), gbar = mapa(sb + BAR_G, r ^ 1);
    st_async_v4(gdst, ag[0][0], ag[0][1], ag[0][2], ag[0][3], gbar);
    st_async_v4(gdst + 4096, ag[1][0], ag[1][1], ag[1][2], ag[1][3], gbar);
  }
  {
    float acc[32];
    const uint32_t xdesc = desc_k(sb + OFF_X);
#pragma unroll
    for (int kc = 0; kc < 4; kc++) {
      mbar_wait(sb + BAR_X + 8 * kc, 0);
#pragma unroll
      for (int tap = 0; tap < 3; tap++) {
        const int j = kc * 3 + tap;
        WAIT_FULL(W1_SLOT(j), W1_USE(j), 8 + j);
        wg_fence();
#pragma unroll
        for (int ks = 0; ks < 4; ks++)
          wgmma_ss_n64<1, 0>(acc, ADESC(W1_SLOT(j), ks), xdesc + kc * 1024 + (tap == 1 ? 0 : 512) + (tap == 0 ? 0 : 8) + ks * 2, (j | ks) != 0);
        wg_commit();
        if (j > 0) { wg_wait<1>(); RELEASE(W1_SLOT(j - 1)); }
      }
    }
    mbar_wait_cluster(sb + BAR_G, 0);
    {
      const float4 v0 = lds128(sb + off_g + 4096 + tid * 16), v1 = lds128(sb + off_g + 8192 + tid * 16);
      ag[0][0] += v0.x; ag[0][1] += v0.y; ag[0][2] += v0.z; ag[0][3] += v0.w;
      ag[1][0] += v1.x; ag[1][1] += v1.y; ag[1][2] += v1.z; ag[1][3] += v1.w;
    }
    wg_wait<0>();
    RELEASE(W1_SLOT(11));
    bar_sync<1, 256>();
    const uint32_t hch = sb + OFF_H + (r2 + w) * 8192;
#pragma unroll
    for (int j = 0; j < 8; j += 2) {
      uint32_t p[4];
#pragma unroll
      for (int q = 0; q < 4; q++) p[q] = pack_bf16(gelu_tanh(acc[4 * j + 2 * q]), gelu_tanh(acc[4 * j + 2 * q + 1]));
      const int i = 8 * (j + (mi >> 1)) + l8;
      const int cidx = 2 * wq + (mi & 1);
      const int s = i >> 1;
      stsm_x4_t(hch + (i & 1) * 4096 + s * 128 + ((cidx ^ (s & 7)) << 4), p[0], p[1], p[2], p[3]);
    }
    fence_async();
    if (w == 0) bar_sync<2, 128>(); else bar_sync<3, 128>();
    if ((tid & 127) == 0) {
      bulk_s2s(mapa(hch, r ^ 1), hch, 8192, mapa(sb + BAR_H + 8 * (r2 + w), r ^ 1));
      mbar_arrive(sb + BAR_H + 8 * (r2 + w));
    }
  }

  {
    float acc[16];
    const uint32_t edesc = desc_mn(sb + OFF_E + w * 8192);
#pragma unroll
    for (int idx = 0; idx < 4; idx++) {
      const uint32_t kc = (idx + r2) & 3;
      if (idx < 2) mbar_wait(sb + BAR_H + 8 * kc, 0); else mbar_wait_cluster(sb + BAR_H + 8 * kc, 0);
      const uint32_t hdesc = desc_k(sb + OFF_H + kc * 8192);
#pragma unroll
      for (int tap = 0; tap < 3; tap++) {
        const int j = idx * 3 + tap;
        if (j < 9) WAIT_FULL(W2_SLOT(j), W2_USE(j), 20 + j);
        else { mbar_wait(sb + BAR_E + 8 * (j - 9), 0); }
        wg_fence();
#pragma unroll
        for (int ks = 0; ks < 4; ks++)
          wgmma_ss_n32<1, 0>(acc, j < 9 ? ADESC(W2_SLOT(j), ks) : edesc + (j - 9) * 1024 + ks * 128,
                             hdesc + (tap == 1 ? 256 : 0) + (tap == 2 ? 8 : 0) + ks * 2, (j | ks) != 0);
        wg_commit();
        if (j > 0 && j <= 9) { wg_wait<1>(); RELEASE(W2_SLOT(j - 1)); }
      }
    }
    wg_wait<0>();
    if (lane == 0) mbar_arrive(sb + BAR_XF);
    const uint32_t fch = sb + OFF_F + w * 4096;
#pragma unroll
    for (int j = 0; j < 4; j += 2) {
      uint32_t p[4];
#pragma unroll
      for (int q = 0; q < 4; q++) p[q] = pack_bf16(gelu_tanh(acc[4 * j + 2 * q]), gelu_tanh(acc[4 * j + 2 * q + 1]));
      const int s = 8 * (j + (mi >> 1)) + l8;
      const int cidx = 2 * wq + (mi & 1);
      stsm_x4_t(fch + s * 128 + ((cidx ^ (s & 7)) << 4), p[0], p[1], p[2], p[3]);
    }
    fence_async();
    bar_sync<1, 256>();
    if ((tid & 127) == 0)
      bulk_s2s(mapa(sb + OFF_FR + w * 2048, r ^ 1), fch + (r ^ 1) * 2048, 2048, mapa(sb + BAR_P, r ^ 1));
  }

  {
    float af[2][8];
#pragma unroll
    for (int j = 0; j < 8; j++) {
      const int slot = j < 4 ? 4 + j : j - 4;
      if (j == 4) {
        mbar_wait_cluster(sb + BAR_P, 0);
        asm volatile("barrier.cluster.arrive.relaxed.aligned;" ::: "memory");
      }
      WAIT_FULL(slot, j <= 4 ? (j < 4 ? 3 : 4) : 3, 32 + j);
      const uint32_t fdesc = j < 4 ? desc_k(sb + OFF_F + (j >> 1) * 4096 + r * 2048) : desc_k(sb + OFF_FR + ((j >> 1) - 2) * 2048);
      wg_fence();
#pragma unroll
      for (int ks = 0; ks < 4; ks++) wgmma_ss_n16<1, 0>(af[j & 1], ADESC(slot, ks), fdesc + ks * 2, ((j >> 1) | ks) != 0);
      wg_commit();
      if (j > 0) { wg_wait<1>(); RELEASE(j - 1 < 4 ? 3 + j : j - 5); }
    }
    stsm_x4_t(sb + OFF_GE + l8 * FE_PITCH + (64 * (2 * (mi >> 1) + w) + 16 * wq + 8 * (mi & 1)) * 2, pack_bf16(ag[0][0], ag[0][1]),
              pack_bf16(ag[0][2], ag[0][3]), pack_bf16(ag[1][0], ag[1][1]), pack_bf16(ag[1][2], ag[1][3]));
    mbar_wait(sb + BAR_WA, 0);
    wg_wait<0>();
    RELEASE(3);
#pragma unroll
    for (int p = 0; p < 2; p++) {
      const int e0 = 64 * (2 * p + w) + 16 * wq;
      const int tl = 8 * (mi >> 1) + l8;
      stsm_x4_t(sb + OFF_FE + tl * FE_PITCH + (e0 + 8 * (mi & 1)) * 2, pack_bf16(af[p][0], af[p][1]), pack_bf16(af[p][2], af[p][3]),
                pack_bf16(af[p][4], af[p][5]), pack_bf16(af[p][6], af[p][7]));
    }
    bar_sync<1, 256>();
  }

  {
    uint32_t A[16][4];
    float acc0[32], acc1[32];
    const int tl0 = 8 * w + 2 * wq;
    const uint32_t fe0 = sb + OFF_FE + tl0 * FE_PITCH + (lane & 3) * 4;
    const uint32_t fe1 = fe0 + FE_PITCH;
    const uint32_t gea = sb + OFF_GE + l8 * FE_PITCH + mi * 16;
    const uint32_t odesc = desc_mn(ring);
    const uint32_t oadesc = desc_mn(sb + OFF_E + 16384);
#define ODESC(q, ks) (((q) < 2 ? ((ks) < 8 ? oadesc + ((ks) >> 2) * 1024 : odesc + (2 + ((ks) >> 2)) * 1024) : odesc + ((ks) >> 2) * 1024) + ((q) & 1) * 512 + ((ks) & 3) * 128)
    const int trow = 16 * r + tl0;
    const bool v0 = (trow < kR) && (a + trow < kT2);
    const bool v1 = (trow + 1 < kR) && (a + trow + 1 < kT2);
    const int orow = (b * kT2 + a + trow) * 8;
    const uint32_t stg_lane = (warp * 2) * 2048 + (mi & 1) * 1024 + l8 * 128;
#define EPILOGUE(acc, q)                                                                                             \
  do {                                                                                                               \
    const uint32_t stg = sb + ((q) < 2 ? OFF_H : OFF_STG2) + ((q) & 1) * 2048;                                       \
    _Pragma("unroll") for (int j = 0; j < 8; j += 2)                                                                 \
        stsm_x4(stg + stg_lane + (((j + (mi >> 1)) ^ l8) << 4), pack_bf16(acc[4 * j], acc[4 * j + 1]),               \
                pack_bf16(acc[4 * j + 2], acc[4 * j + 3]), pack_bf16(acc[4 * j + 4], acc[4 * j + 5]),                \
                pack_bf16(acc[4 * j + 6], acc[4 * j + 7]));                                                          \
    fence_async();                                                                                                   \
    __syncwarp();                                                                                                    \
    if (lane == 0) {                                                                                                 \
      if (v1) tma_store3d(&mout, stg + warp * 4096, 0, orow, q);                                                     \
      else if (v0) tma_store3d(&mout8, stg + warp * 4096, 0, orow, q);                                               \
      asm volatile("cp.async.bulk.commit_group;" ::: "memory");                                                      \
    }                                                                                                                \
  } while (0)
    uint32_t G[2][8], X[2][8], Y[2][8];
#define LOADGRP(buf, kc)                                                                                   \
  do {                                                                                                     \
    ldsm_x4(gea + (kc) * 128, G[buf][0], G[buf][1], G[buf][2], G[buf][3]);                                 \
    ldsm_x4(gea + (kc) * 128 + 64, G[buf][4], G[buf][5], G[buf][6], G[buf][7]);                            \
    _Pragma("unroll") for (int c = 0; c < 8; c++) {                                                        \
      X[buf][c] = lds32(fe0 + (kc) * 128 + c * 16);                                                        \
      Y[buf][c] = lds32(fe1 + (kc) * 128 + c * 16);                                                        \
    }                                                                                                      \
  } while (0)
#define MMA0(ks) wgmma_rs_n64<1>(acc0, A[ks][0], A[ks][1], A[ks][2], A[ks][3], ODESC(0, ks), (ks) != 0)
    LOADGRP(0, 0);
    if (w == 1) bar_sync<5, 256>();
#pragma unroll
    for (int kc = 0; kc < 4; kc++) {
      if (kc < 3) { LOADGRP((kc + 1) & 1, kc + 1); }
#pragma unroll
      for (int k = 0; k < 4; k++) {
        const int ks = 4 * kc + k;
        A[ks][0] = joint2(X[kc & 1][2 * k], G[kc & 1][2 * k]);
        A[ks][1] = joint2(Y[kc & 1][2 * k], G[kc & 1][2 * k]);
        A[ks][2] = joint2(X[kc & 1][2 * k + 1], G[kc & 1][2 * k + 1]);
        A[ks][3] = joint2(Y[kc & 1][2 * k + 1], G[kc & 1][2 * k + 1]);
        if ((k & 1) && ks > 1) {
          wg_fence();
          MMA0(ks - 3); MMA0(ks - 2);
        }
      }
    }
    if (w == 0) bar_arrive<5, 256>();
    wg_fence();
    MMA0(14); MMA0(15);
    wg_commit();
#pragma unroll
    for (int ks = 0; ks < 16; ks++) wgmma_rs_n64<1>(acc1, A[ks][0], A[ks][1], A[ks][2], A[ks][3], ODESC(1, ks), ks != 0);
    wg_commit();
    wg_wait<1>();
    EPILOGUE(acc0, 0);
    mbar_wait(sb + BAR_WO, 0);
    wg_fence();
#pragma unroll
    for (int ks = 0; ks < 16; ks++) wgmma_rs_n64<1>(acc0, A[ks][0], A[ks][1], A[ks][2], A[ks][3], ODESC(2, ks), ks != 0);
    wg_commit();
    wg_wait<1>();
    EPILOGUE(acc1, 1);
    wg_fence();
#pragma unroll
    for (int ks = 0; ks < 16; ks++) wgmma_rs_n64<1>(acc1, A[ks][0], A[ks][1], A[ks][2], A[ks][3], ODESC(3, ks), ks != 0);
    wg_commit();
    wg_wait<1>();
    EPILOGUE(acc0, 2);
    wg_wait<0>();
    EPILOGUE(acc1, 3);
    if (lane == 0) asm volatile("cp.async.bulk.wait_group.read 0;" ::: "memory");
    __syncwarp();
    asm volatile("barrier.cluster.wait.aligned;" ::: "memory");
  }
  } else {
    const int pw = warp - 8;
    const uint32_t so = sb + pw * 8;
    const uint32_t sd = sb + OFF_RING + pw * 16384;
    const int prow = 64 * (pw >> 1), pblk = 2 * (pw & 1);
    if (lane == 0) {
      mbar_init(so + BAR_FULL, 1);
      mbar_init(so + BAR_FULL + 32, 1);
      mbar_init(so + BAR_X, 1);
      mbar_init(sb + BAR_E + 8 * ((pw + 3) & 3), pw == 0 ? 4 : 1);
      asm volatile("fence.mbarrier_init.release.cluster;" ::: "memory");
      mbar_expect_tx(so + BAR_FULL, pw == 2 ? 16384 + 2048 : 16384);
      tma3d(sd, &mwg, 0, 64 * r2 + prow, pblk, so + BAR_FULL);
      if (pw == 2) tma3d(sb + off_g, &mg, 0, b * 8, r2, so + BAR_FULL);
      mbar_expect_tx(so + BAR_FULL + 32, 16384);
      tma3d(sd + 65536, &mw1, 0, pw == 3 ? 64 : pw * 256, r2, so + BAR_FULL + 32);
      if (pw == 0) {
        mbar_expect_tx(so + BAR_X, 16384);
        tma4d(sb + OFF_X + pw * 16384, &mx, pw * 64, 2 * a - 2, 0, b, so + BAR_X);
      }
    }
    __syncwarp();
    bar_sync<4, 384>();
    asm volatile("barrier.cluster.arrive.relaxed.aligned;" ::: "memory");
    if (lane == 0) {
      if (pw >= 1) {
        while (clock64() - t_start < XDELAY + (pw - 1) * XSTEP) {}
        mbar_expect_tx(so + BAR_X, 16384);
        tma4d(sb + OFF_X + pw * 16384, &mx, pw * 64, 2 * a - 2, 0, b, so + BAR_X);
      }
      if (pw == 1) { prefetch_map(&mw2); prefetch_map(&mwf); }
      else if (pw == 2) { prefetch_map(&mwo); prefetch_map(&mout); prefetch_map(&mout8); }
#define ISSUE(hi, use, map, row, blk, tr)                                                     \
  do {                                                                                        \
    mbar_wait(so + BAR_EMPTY + 32 * (hi), ((use) - 1) & 1);                                   \
    mbar_expect_tx(so + BAR_FULL + 32 * (hi), 16384);                                         \
    tma3d(sd + 65536 * (hi), map, 0, row, blk, so + BAR_FULL + 32 * (hi));                    \
  } while (0)
#define CONV_ROW(j, rot) ((((j) - 3 * (((j) * 11) >> 5)) << 8) + (((((j) * 11) >> 5) + (rot)) & 3) * 64)
      ISSUE(0, 1, &mw1, CONV_ROW(4 + pw, 0), r2, 12 + pw);
      ISSUE(1, 1, &mw1, CONV_ROW(8 + pw, 0), r2, 16 + pw);
      if (pw == 3 && blockIdx.x < 128) {
        prefetch_l2(pw2 + blockIdx.x * 3072, 3072);
        prefetch_l2(pwf + blockIdx.x * 1024, 1024);
        prefetch_l2(pwo + blockIdx.x * 1024, 1024);
      }
#define ISSUE_E(e)                                                                                   \
  do {                                                                                               \
    mbar_expect_tx(sb + BAR_E + 8 * (e), 16384);                                                     \
    tma3d(sb + OFF_E + (e) * 16384, &mw2, 0, CONV_ROW(9 + (e), r2), r2, sb + BAR_E + 8 * (e));       \
  } while (0)
      ISSUE(0, 2, &mw2, CONV_ROW(pw, r2), r2, 20 + pw);
      if (pw == 1) ISSUE_E(0);
      ISSUE(1, 2, &mw2, CONV_ROW(4 + pw, r2), r2, 24 + pw);
      if (pw == 0) ISSUE_E(1);
      if (pw == 3) ISSUE_E(2);
      const uint32_t lp = pw == 0;
      if (pw == 0) ISSUE(0, 3, &mw2, CONV_ROW(8, r2), r2, 28);
      ISSUE(1, 3, &mwf, 64 * r2 + prow, pblk, 32 + pw);
      ISSUE(0, 3 + lp, &mwf, 128 - 64 * r2 + prow, pblk, 36 + pw);
      if (pw >= 2) mbar_wait(sb + BAR_XF, 0); else mbar_wait(so + BAR_EMPTY + 32, 1);
      mbar_expect_tx(sb + BAR_WA, 16384);
      tma3d(pw >= 2 ? sb + OFF_E + (pw - 1) * 16384 : sd + 65536, &mwo, 0, 64 * (pw ^ 2), 0, sb + BAR_WA);
      mbar_wait(so + BAR_EMPTY, lp ^ 1);
      mbar_expect_tx(sb + BAR_WO, 16384);
      tma3d(sd, &mwo, 0, 64 * pw, 2, sb + BAR_WO);
    }
  }
}

typedef CUresult (*EncodeFn)(CUtensorMap*, CUtensorMapDataType, cuuint32_t, void*, const cuuint64_t*, const cuuint64_t*,
                             const cuuint32_t*, const cuuint32_t*, CUtensorMapInterleave, CUtensorMapSwizzle,
                             CUtensorMapL2promotion, CUtensorMapFloatOOBfill);

struct Maps { CUtensorMap x, w1, w2, wf, wg, wo, g, out, out8; };

void make_w_map(EncodeFn enc, CUtensorMap* m, const void* p, uint64_t rows, uint32_t box_rows, uint32_t box_blks = 2) {
  cuuint64_t gd[3] = {64, rows, 4};
  cuuint64_t gs[2] = {512, 128};
  cuuint32_t box[3] = {64, box_rows, box_blks};
  cuuint32_t es[3] = {1, 1, 1};
  enc(m, CU_TENSOR_MAP_DATA_TYPE_BFLOAT16, 3, const_cast<void*>(p), gd, gs, box, es, CU_TENSOR_MAP_INTERLEAVE_NONE,
      CU_TENSOR_MAP_SWIZZLE_128B, CU_TENSOR_MAP_L2_PROMOTION_L2_256B, CU_TENSOR_MAP_FLOAT_OOB_FILL_NONE);
}

}

extern "C" void kernel_launch(void* const* d_in, const int* in_sizes, int n_in, void* d_out, int out_size) {
  static Maps maps;
  static const void* cached[8] = {nullptr};
  static EncodeFn enc = nullptr;
  if (!enc) {
    void* fn = nullptr;
    cudaDriverEntryPointQueryResult qr;
    cudaGetDriverEntryPoint("cuTensorMapEncodeTiled", &fn, cudaEnableDefault, &qr);
    enc = (EncodeFn)fn;
    cudaFuncSetAttribute(joint_kernel, cudaFuncAttributeMaxDynamicSharedMemorySize, SMEM_BYTES);
  }
  bool same = cached[7] == d_out;
  for (int i = 0; i < 7; i++) same = same && (cached[i] == d_in[i]);
  if (!same) {
    for (int i = 0; i < 7; i++) cached[i] = d_in[i];
    cached[7] = d_out;
    {
      cuuint64_t gd[4] = {256, 2000, 2, 2};
      cuuint64_t gs[3] = {1024, 512, 4000ull * 512};
      cuuint32_t box[4] = {64, 64, 2, 1};
      cuuint32_t es[4] = {1, 1, 1, 1};
      enc(&maps.x, CU_TENSOR_MAP_DATA_TYPE_BFLOAT16, 4, d_in[0], gd, gs, box, es, CU_TENSOR_MAP_INTERLEAVE_NONE,
          CU_TENSOR_MAP_SWIZZLE_128B, CU_TENSOR_MAP_L2_PROMOTION_L2_128B, CU_TENSOR_MAP_FLOAT_OOB_FILL_NONE);
    }
    make_w_map(enc, &maps.w1, d_in[1], 768, 64);
    make_w_map(enc, &maps.w2, d_in[2], 768, 64);
    make_w_map(enc, &maps.g, d_in[3], 16, 8);
    make_w_map(enc, &maps.wf, d_in[4], 256, 64);
    make_w_map(enc, &maps.wg, d_in[5], 256, 64);
    make_w_map(enc, &maps.wo, d_in[6], 256, 64);
    make_w_map(enc, &maps.out, d_out, 16000, 16, 1);
    make_w_map(enc, &maps.out8, d_out, 16000, 8, 1);
  }
  joint_kernel<<<132, 384, SMEM_BYTES>>>(maps.x, maps.w1, maps.w2, maps.wf, maps.wg, maps.wo, maps.g, maps.out, maps.out8,
                                         (const uint8_t*)d_in[2], (const uint8_t*)d_in[4], (const uint8_t*)d_in[6]);
}
```
